```python
import torch

def _softmax(x, axis=-1):
    return torch.softmax(x, dim=axis)
def _gelu(x):
    return torch.nn.functional.gelu(x, approximate="tanh")
def _silu(x):
    return torch.nn.functional.silu(x)
def _sigmoid(x):
    return torch.sigmoid(x)
def _layernorm(x, axis=-1, eps=1e-5):
    m = x.mean(dim=axis, keepdim=True)
    v = x.var(dim=axis, keepdim=True, unbiased=False)
    return (x - m) / torch.sqrt(v + eps)
def _scatter_add(tgt, idx, src, axis=0):
    return tgt.clone().index_add_(axis, idx, src)
def _segment_sum(src, seg, n):
    out = torch.zeros((n,) + src.shape[1:], dtype=src.dtype)
    return out.index_add_(0, seg, src)
def _pad(x, pw):
    flat = tuple(v for pair in reversed(pw) for v in pair)
    return torch.nn.functional.pad(x, flat)

kernel_name = 'standalone__batchnorm__sampling'

def setup_inputs():

    _w = (lambda a: (lambda t: t.to(torch.bfloat16) if t.is_floating_point() else t)(torch.as_tensor(a)))
    B, S, C = 1024, 32, 448
    K = 3
    return {
        "x": _w((lambda *s: torch.randn(*s, dtype=torch.bfloat16) * 0.05)(B, S, C)),
        "w": _w((lambda *s: torch.randn(*s, dtype=torch.bfloat16) * 0.05)(K, C, C) * (1.0 / (K * C) ** 0.5)),
        "mean": _w((lambda *s: torch.randn(*s, dtype=torch.bfloat16) * 0.05)(C) * 0.1),
        "var": _w(torch.abs((lambda *s: torch.randn(*s, dtype=torch.bfloat16) * 0.05)(C)) + 0.5),
        "g": _w((lambda *s: torch.randn(*s, dtype=torch.bfloat16) * 0.05)(C) + 1.0),
        "b": _w((lambda *s: torch.randn(*s, dtype=torch.bfloat16) * 0.05)(C) * 0.1),
    }

def reference(x, w, mean, var, g, b):
    K = 3
    P = K // 2
    S = x.shape[1]
    xp = _pad(x, ((0, 0), (P, P), (0, 0)))
    y = sum(torch.einsum('bsc,cd->bsd', xp[:, k:k + S, :], w[k]) for k in range(K))
    inv_std = 1.0 / torch.sqrt(var + 1e-5)
    y = (y - mean) * (g * inv_std) + b
    return _silu(y)
```

```cpp
#include <cuda_runtime.h>
#include <cuda_bf16.h>
#include <cuda.h>
#include <stdint.h>

namespace {

constexpr int C = 448, S = 32, NB = 1024;
constexpr int GRID = 128;
constexpr int XSLOT = 32 * 1024;
constexpr int WST = 14336;
constexpr int NWS = 7;
constexpr int RND = NWS * WST;
constexpr int NRND = 8;
constexpr int OFF_W = 0;
constexpr int OFF_STG = OFF_W + NWS * WST;
constexpr int OFF_X = OFF_STG + 8 * 2048;
constexpr int OFF_SHIFT = OFF_X + 3 * XSLOT + XSLOT / 2;
constexpr int WRAW = 16384;
constexpr int OFF_SCALE = OFF_W + NWS * WRAW;
constexpr int OFF_BAR = OFF_SHIFT + 896;
constexpr int SMEM_BYTES = OFF_BAR + 128;
constexpr int BAR_WFULL = OFF_BAR, BAR_WEMPTY = OFF_BAR + 56, BAR_XFULL = OFF_BAR + 88, BAR_WARM = OFF_BAR + 120, NBARS = 16;
constexpr int NHELP = 4;
constexpr int HA = 56, HB = 65;
constexpr uint32_t SMEM_BASE = 1024;

__device__ __align__(1024) uint8_t g_wt[2 * NRND * RND];
__device__ unsigned g_sync[64];

#define SPIN(bar, par, done) "LAB_WAIT:\nmbarrier.try_wait.parity.shared::cta.b64 p, [" bar "], " par ";\n@!p bra.uni LAB_WAIT;\n"

__device__ __forceinline__ uint32_t smem_u32(const void* p) { return (uint32_t)__cvta_generic_to_shared(p); }
__device__ __forceinline__ void mbar_init(uint32_t bar, uint32_t cnt) { asm volatile("mbarrier.init.shared::cta.b64 [%0], %1;" ::"r"(bar), "r"(cnt) : "memory"); }
__device__ __forceinline__ uint32_t mbar_test(uint32_t bar, uint32_t parity) {
  uint32_t ok;
  asm volatile("{\n.reg .pred p;\nmbarrier.try_wait.parity.shared::cta.b64 p, [%1], %2;\nselp.u32 %0, 1, 0, p;\n}" : "=r"(ok) : "r"(bar), "r"(parity) : "memory");
  return ok;
}
__device__ __forceinline__ void mbar_wait_tok(uint32_t bar, uint32_t parity, uint32_t tok) {
  asm volatile("{\n.reg .pred p;\n.reg .u32 c;\nsetp.ne.u32 p, %2, 0;\n@p bra.uni LAB_DONE;\n" SPIN("%0", "%1", "LAB_DONE") "LAB_DONE:\n}"
               ::"r"(bar), "r"(parity), "r"(tok) : "memory");
}
__device__ __forceinline__ void mbar_wait(uint32_t bar, uint32_t parity) {
  asm volatile("{\n.reg .pred p;\n.reg .u32 c;\n" SPIN("%0", "%1", "LAB_DONE") "LAB_DONE:\n}" ::"r"(bar), "r"(parity) : "memory");
}
__device__ __forceinline__ unsigned flag_load(const unsigned* sync, int level, bool pred) {
  unsigned v;
  asm volatile("{\n.reg .pred p;\n.reg .u64 a;\nmov.u32 %0, 0;\nsetp.eq.u32 p, %3, 0;\n@p bra.uni LAB_SKIP;\n"
               "mad.wide.u32 a, %2, 4, %1;\nld.relaxed.gpu.global.u32 %0, [a + 128];\nLAB_SKIP:\n}"
               : "=r"(v) : "l"(sync), "r"(level), "r"((uint32_t)pred) : "memory");
  return v;
}
__device__ __forceinline__ void flag_wait(const unsigned* sync, int level, unsigned sample, unsigned target, bool pred) {
  asm volatile(
      "{\n.reg .pred p;\n.reg .u32 c, v;\n.reg .s32 d;\n.reg .u64 a;\n"
      "setp.eq.u32 p, %4, 0;\n@p bra.uni LAB_DONE;\n"
      "mov.u32 c, 0;\nmov.u32 v, %2;\n"
      "LAB_WAIT:\n"
      "sub.s32 d, v, %3;\nsetp.ge.s32 p, d, 0;\nvote.sync.all.pred p, p, 0xffffffff;\n@p bra.uni LAB_DONE;\n"
      "mad.wide.u32 a, %1, 4, %0;\nld.relaxed.gpu.global.u32 v, [a + 128];\n"
      "add.u32 c, c, 1;\nsetp.lt.u32 p, c, 4000000;\n@p bra.uni LAB_WAIT;\ntrap;\n"
      "LAB_DONE:\n}" ::"l"(sync), "r"(level), "r"(sample), "r"(target), "r"((uint32_t)pred) : "memory");
}
__device__ __forceinline__ void tma_load_x(uint32_t dst, const CUtensorMap* m, uint32_t bar, uint32_t bytes, int c0, int hs, int h, int pair, int t, bool pred) {
  asm volatile("{\n.reg .pred p;\n.reg .b32 c, b;\nsetp.eq.u32 p, %7, 0;\n@p bra.uni LAB_SKIP;\nelect.sync _|p, 0xffffffff;\n"
               "mad.lo.s32 c, %8, %9, %3;\nmad.lo.s32 b, %10, 64, %4;\nshl.b32 b, b, 3;\n"
               "@p mbarrier.arrive.expect_tx.shared::cta.b64 _, [%2], %6;\n"
               "@p cp.async.bulk.tensor.3d.shared::cluster.global.mbarrier::complete_tx::bytes [%0], [%1, {c,b,%5}], [%2];\nLAB_SKIP:\n}"
               ::"r"(dst), "l"(m), "r"(bar), "r"(c0), "r"(pair), "r"(0), "r"(bytes), "r"((uint32_t)pred), "r"(h), "r"(hs), "r"(t) : "memory");
}
__device__ __forceinline__ void tma_load_w_raw(uint32_t dst, const CUtensorMap* ma, const CUtensorMap* mb, uint32_t bar, int k, int blk, int col, bool pred) {
  asm volatile("{\n.reg .pred p;\nsetp.eq.u32 p, %9, 0;\n@p bra.uni LAB_SKIP;\nelect.sync _|p, 0xffffffff;\n"
               "@p mbarrier.arrive.expect_tx.shared::cta.b64 _, [%3], %7;\n"
               "@p cp.async.bulk.tensor.4d.shared::cluster.global.mbarrier::complete_tx::bytes [%0], [%1, {%8,%4,%8,%5}], [%3];\n"
               "@p cp.async.bulk.tensor.3d.shared::cluster.global.mbarrier::complete_tx::bytes [%0 + 12288], [%2, {%6,%4,%8}], [%3];\nLAB_SKIP:\n}"
               ::"r"(dst), "l"(ma), "l"(mb), "r"(bar), "r"(k), "r"(blk), "r"(col), "n"(WRAW), "r"(0), "r"((uint32_t)pred) : "memory");
}
__device__ __forceinline__ void tma_store_4d(const CUtensorMap* m, uint32_t src, int c0, int c1, int c2, int c3) {
  asm volatile("{\n.reg .pred p;\nelect.sync _|p, 0xffffffff;\n"
               "@p cp.async.bulk.tensor.4d.global.shared::cta.bulk_group [%0, {%2,%3,%4,%5}], [%1];\n"
               "cp.async.bulk.commit_group;\n}"
               ::"l"(m), "r"(src), "r"(c0), "r"(c1), "r"(c2), "r"(c3) : "memory");
}
__device__ __forceinline__ void prefetch_l2(const void* src, int i8, int i4, int i, bool pred) {
  asm volatile("{\n.reg .pred p;\n.reg .u32 o;\n.reg .u64 a;\nsetp.eq.u32 p, %4, 0;\n@p bra.uni LAB_SKIP;\nelect.sync _|p, 0xffffffff;\n"
               "mad.lo.u32 o, %1, 8, %3;\nmad.lo.u32 o, %2, 4, o;\nmad.wide.u32 a, o, 14336, %0;\n@p cp.async.bulk.prefetch.L2.global [a], 14336;\nLAB_SKIP:\n}"
               ::"l"(src), "r"(i8), "r"(i4), "r"(i), "r"((uint32_t)pred) : "memory");
}
__device__ __forceinline__ void prefetch_tensor_3d(const CUtensorMap* m, int c0, int c1, bool pred) {
  asm volatile("{\n.reg .pred p;\nsetp.eq.u32 p, %4, 0;\n@p bra.uni LAB_SKIP;\nelect.sync _|p, 0xffffffff;\n"
               "@p cp.async.bulk.prefetch.tensor.3d.L2.global [%0, {%1,%2,%3}];\nLAB_SKIP:\n}"
               ::"l"(m), "r"(c0), "r"(c1), "r"(0), "r"((uint32_t)pred) : "memory");
}
__device__ __forceinline__ void ldsm4(uint32_t addr, uint32_t (&r)[4]) {
  asm volatile("ldmatrix.sync.aligned.m8n8.x4.shared.b16 {%0,%1,%2,%3}, [%4];" : "=r"(r[0]), "=r"(r[1]), "=r"(r[2]), "=r"(r[3]) : "r"(addr) : "memory");
}
__device__ __forceinline__ void ldsm2(uint32_t addr, uint32_t (&r)[2]) {
  asm volatile("ldmatrix.sync.aligned.m8n8.x2.shared.b16 {%0,%1}, [%2];" : "=r"(r[0]), "=r"(r[1]) : "r"(addr) : "memory");
}
__device__ __forceinline__ void stsm4(uint32_t addr, uint32_t r0, uint32_t r1, uint32_t r2, uint32_t r3) {
  asm volatile("stmatrix.sync.aligned.m8n8.x4.shared.b16 [%0], {%1,%2,%3,%4};" ::"r"(addr), "r"(r0), "r"(r1), "r"(r2), "r"(r3) : "memory");
}
__device__ __forceinline__ uint32_t pack_bf16(float lo, float hi) { uint32_t r; asm volatile("cvt.rn.bf16x2.f32 %0, %1, %2;" : "=r"(r) : "f"(hi), "f"(lo)); return r; }
__device__ __forceinline__ void wg_fence() { asm volatile("wgmma.fence.sync.aligned;" ::: "memory"); }
__device__ __forceinline__ void wg_commit() { asm volatile("wgmma.commit_group.sync.aligned;" ::: "memory"); }
__device__ __forceinline__ void wg_wait0() { asm volatile("wgmma.wait_group.sync.aligned 0;" ::: "memory"); }
__device__ __forceinline__ void fence_acc(float (&d)[112]) {
#pragma unroll
  for (int i = 0; i < 112; i++) asm volatile("" : "+f"(d[i])::"memory");
}
__device__ __forceinline__ void wgmma_acc(float (&d)[112], uint64_t descB) {
  asm volatile("wgmma.mma_async.sync.aligned.m64n224k16.f32.bf16.bf16 "
               "{%0, %1, %2, %3, %4, %5, %6, %7, %8, %9, %10, %11, %12, %13, %14, %15, "
               "%16, %17, %18, %19, %20, %21, %22, %23, %24, %25, %26, %27, %28, %29, %30, %31, "
               "%32, %33, %34, %35, %36, %37, %38, %39, %40, %41, %42, %43, %44, %45, %46, %47, "
               "%48, %49, %50, %51, %52, %53, %54, %55, %56, %57, %58, %59, %60, %61, %62, %63, "
               "%64, %65, %66, %67, %68, %69, %70, %71, %72, %73, %74, %75, %76, %77, %78, %79, "
               "%80, %81, %82, %83, %84, %85, %86, %87, %88, %89, %90, %91, %92, %93, %94, %95, "
               "%96, %97, %98, %99, %100, %101, %102, %103, %104, %105, %106, %107, %108, %109, %110, %111}, "
               "{FA0, FA1, FA2, FA3}, %112, 1, 1, 1, 1;"
               : "+f"(d[0]), "+f"(d[1]), "+f"(d[2]), "+f"(d[3]), "+f"(d[4]), "+f"(d[5]), "+f"(d[6]), "+f"(d[7]),
                 "+f"(d[8]), "+f"(d[9]), "+f"(d[10]), "+f"(d[11]), "+f"(d[12]), "+f"(d[13]), "+f"(d[14]), "+f"(d[15]),
                 "+f"(d[16]), "+f"(d[17]), "+f"(d[18]), "+f"(d[19]), "+f"(d[20]), "+f"(d[21]), "+f"(d[22]), "+f"(d[23]),
                 "+f"(d[24]), "+f"(d[25]), "+f"(d[26]), "+f"(d[27]), "+f"(d[28]), "+f"(d[29]), "+f"(d[30]), "+f"(d[31]),
                 "+f"(d[32]), "+f"(d[33]), "+f"(d[34]), "+f"(d[35]), "+f"(d[36]), "+f"(d[37]), "+f"(d[38]), "+f"(d[39]),
                 "+f"(d[40]), "+f"(d[41]), "+f"(d[42]), "+f"(d[43]), "+f"(d[44]), "+f"(d[45]), "+f"(d[46]), "+f"(d[47]),
                 "+f"(d[48]), "+f"(d[49]), "+f"(d[50]), "+f"(d[51]), "+f"(d[52]), "+f"(d[53]), "+f"(d[54]), "+f"(d[55]),
                 "+f"(d[56]), "+f"(d[57]), "+f"(d[58]), "+f"(d[59]), "+f"(d[60]), "+f"(d[61]), "+f"(d[62]), "+f"(d[63]),
                 "+f"(d[64]), "+f"(d[65]), "+f"(d[66]), "+f"(d[67]), "+f"(d[68]), "+f"(d[69]), "+f"(d[70]), "+f"(d[71]),
                 "+f"(d[72]), "+f"(d[73]), "+f"(d[74]), "+f"(d[75]), "+f"(d[76]), "+f"(d[77]), "+f"(d[78]), "+f"(d[79]),
                 "+f"(d[80]), "+f"(d[81]), "+f"(d[82]), "+f"(d[83]), "+f"(d[84]), "+f"(d[85]), "+f"(d[86]), "+f"(d[87]),
                 "+f"(d[88]), "+f"(d[89]), "+f"(d[90]), "+f"(d[91]), "+f"(d[92]), "+f"(d[93]), "+f"(d[94]), "+f"(d[95]),
                 "+f"(d[96]), "+f"(d[97]), "+f"(d[98]), "+f"(d[99]), "+f"(d[100]), "+f"(d[101]), "+f"(d[102]), "+f"(d[103]),
                 "+f"(d[104]), "+f"(d[105]), "+f"(d[106]), "+f"(d[107]), "+f"(d[108]), "+f"(d[109]), "+f"(d[110]), "+f"(d[111])
               : "l"(descB));
}
__device__ __forceinline__ void wgmma_first(float (&d)[112], uint64_t descB) {
  asm volatile("wgmma.mma_async.sync.aligned.m64n224k16.f32.bf16.bf16 "
               "{%0, %1, %2, %3, %4, %5, %6, %7, %8, %9, %10, %11, %12, %13, %14, %15, "
               "%16, %17, %18, %19, %20, %21, %22, %23, %24, %25, %26, %27, %28, %29, %30, %31, "
               "%32, %33, %34, %35, %36, %37, %38, %39, %40, %41, %42, %43, %44, %45, %46, %47, "
               "%48, %49, %50, %51, %52, %53, %54, %55, %56, %57, %58, %59, %60, %61, %62, %63, "
               "%64, %65, %66, %67, %68, %69, %70, %71, %72, %73, %74, %75, %76, %77, %78, %79, "
               "%80, %81, %82, %83, %84, %85, %86, %87, %88, %89, %90, %91, %92, %93, %94, %95, "
               "%96, %97, %98, %99, %100, %101, %102, %103, %104, %105, %106, %107, %108, %109, %110, %111}, "
               "{FA0, FA1, FA2, FA3}, %112, 0, 1, 1, 1;"
               : "=f"(d[0]), "=f"(d[1]), "=f"(d[2]), "=f"(d[3]), "=f"(d[4]), "=f"(d[5]), "=f"(d[6]), "=f"(d[7]),
                 "=f"(d[8]), "=f"(d[9]), "=f"(d[10]), "=f"(d[11]), "=f"(d[12]), "=f"(d[13]), "=f"(d[14]), "=f"(d[15]),
                 "=f"(d[16]), "=f"(d[17]), "=f"(d[18]), "=f"(d[19]), "=f"(d[20]), "=f"(d[21]), "=f"(d[22]), "=f"(d[23]),
                 "=f"(d[24]), "=f"(d[25]), "=f"(d[26]), "=f"(d[27]), "=f"(d[28]), "=f"(d[29]), "=f"(d[30]), "=f"(d[31]),
                 "=f"(d[32]), "=f"(d[33]), "=f"(d[34]), "=f"(d[35]), "=f"(d[36]), "=f"(d[37]), "=f"(d[38]), "=f"(d[39]),
                 "=f"(d[40]), "=f"(d[41]), "=f"(d[42]), "=f"(d[43]), "=f"(d[44]), "=f"(d[45]), "=f"(d[46]), "=f"(d[47]),
                 "=f"(d[48]), "=f"(d[49]), "=f"(d[50]), "=f"(d[51]), "=f"(d[52]), "=f"(d[53]), "=f"(d[54]), "=f"(d[55]),
                 "=f"(d[56]), "=f"(d[57]), "=f"(d[58]), "=f"(d[59]), "=f"(d[60]), "=f"(d[61]), "=f"(d[62]), "=f"(d[63]),
                 "=f"(d[64]), "=f"(d[65]), "=f"(d[66]), "=f"(d[67]), "=f"(d[68]), "=f"(d[69]), "=f"(d[70]), "=f"(d[71]),
                 "=f"(d[72]), "=f"(d[73]), "=f"(d[74]), "=f"(d[75]), "=f"(d[76]), "=f"(d[77]), "=f"(d[78]), "=f"(d[79]),
                 "=f"(d[80]), "=f"(d[81]), "=f"(d[82]), "=f"(d[83]), "=f"(d[84]), "=f"(d[85]), "=f"(d[86]), "=f"(d[87]),
                 "=f"(d[88]), "=f"(d[89]), "=f"(d[90]), "=f"(d[91]), "=f"(d[92]), "=f"(d[93]), "=f"(d[94]), "=f"(d[95]),
                 "=f"(d[96]), "=f"(d[97]), "=f"(d[98]), "=f"(d[99]), "=f"(d[100]), "=f"(d[101]), "=f"(d[102]), "=f"(d[103]),
                 "=f"(d[104]), "=f"(d[105]), "=f"(d[106]), "=f"(d[107]), "=f"(d[108]), "=f"(d[109]), "=f"(d[110]), "=f"(d[111])
               : "l"(descB));
}
__device__ __forceinline__ void wgmma_sd(float (&d)[112], uint64_t descB, int scale_d) {
  asm volatile("{\n.reg .pred p;\nsetp.ne.s32 p, %113, 0;\nwgmma.mma_async.sync.aligned.m64n224k16.f32.bf16.bf16 "
               "{%0, %1, %2, %3, %4, %5, %6, %7, %8, %9, %10, %11, %12, %13, %14, %15, "
               "%16, %17, %18, %19, %20, %21, %22, %23, %24, %25, %26, %27, %28, %29, %30, %31, "
               "%32, %33, %34, %35, %36, %37, %38, %39, %40, %41, %42, %43, %44, %45, %46, %47, "
               "%48, %49, %50, %51, %52, %53, %54, %55, %56, %57, %58, %59, %60, %61, %62, %63, "
               "%64, %65, %66, %67, %68, %69, %70, %71, %72, %73, %74, %75, %76, %77, %78, %79, "
               "%80, %81, %82, %83, %84, %85, %86, %87, %88, %89, %90, %91, %92, %93, %94, %95, "
               "%96, %97, %98, %99, %100, %101, %102, %103, %104, %105, %106, %107, %108, %109, %110, %111}, "
               "{FA0, FA1, FA2, FA3}, %112, p, 1, 1, 1;\n}"
               : "+f"(d[0]), "+f"(d[1]), "+f"(d[2]), "+f"(d[3]), "+f"(d[4]), "+f"(d[5]), "+f"(d[6]), "+f"(d[7]),
                 "+f"(d[8]), "+f"(d[9]), "+f"(d[10]), "+f"(d[11]), "+f"(d[12]), "+f"(d[13]), "+f"(d[14]), "+f"(d[15]),
                 "+f"(d[16]), "+f"(d[17]), "+f"(d[18]), "+f"(d[19]), "+f"(d[20]), "+f"(d[21]), "+f"(d[22]), "+f"(d[23]),
                 "+f"(d[24]), "+f"(d[25]), "+f"(d[26]), "+f"(d[27]), "+f"(d[28]), "+f"(d[29]), "+f"(d[30]), "+f"(d[31]),
                 "+f"(d[32]), "+f"(d[33]), "+f"(d[34]), "+f"(d[35]), "+f"(d[36]), "+f"(d[37]), "+f"(d[38]), "+f"(d[39]),
                 "+f"(d[40]), "+f"(d[41]), "+f"(d[42]), "+f"(d[43]), "+f"(d[44]), "+f"(d[45]), "+f"(d[46]), "+f"(d[47]),
                 "+f"(d[48]), "+f"(d[49]), "+f"(d[50]), "+f"(d[51]), "+f"(d[52]), "+f"(d[53]), "+f"(d[54]), "+f"(d[55]),
                 "+f"(d[56]), "+f"(d[57]), "+f"(d[58]), "+f"(d[59]), "+f"(d[60]), "+f"(d[61]), "+f"(d[62]), "+f"(d[63]),
                 "+f"(d[64]), "+f"(d[65]), "+f"(d[66]), "+f"(d[67]), "+f"(d[68]), "+f"(d[69]), "+f"(d[70]), "+f"(d[71]),
                 "+f"(d[72]), "+f"(d[73]), "+f"(d[74]), "+f"(d[75]), "+f"(d[76]), "+f"(d[77]), "+f"(d[78]), "+f"(d[79]),
                 "+f"(d[80]), "+f"(d[81]), "+f"(d[82]), "+f"(d[83]), "+f"(d[84]), "+f"(d[85]), "+f"(d[86]), "+f"(d[87]),
                 "+f"(d[88]), "+f"(d[89]), "+f"(d[90]), "+f"(d[91]), "+f"(d[92]), "+f"(d[93]), "+f"(d[94]), "+f"(d[95]),
                 "+f"(d[96]), "+f"(d[97]), "+f"(d[98]), "+f"(d[99]), "+f"(d[100]), "+f"(d[101]), "+f"(d[102]), "+f"(d[103]),
                 "+f"(d[104]), "+f"(d[105]), "+f"(d[106]), "+f"(d[107]), "+f"(d[108]), "+f"(d[109]), "+f"(d[110]), "+f"(d[111])
               : "l"(descB), "r"(scale_d));
}

__device__ __forceinline__ float bf_lo(uint32_t v) { return __uint_as_float(v << 16); }
__device__ __forceinline__ float bf_hi(uint32_t v) { return __uint_as_float(v & 0xffff0000u); }

__device__ __forceinline__ float bn_scale(float g, float v) {
  float r;
  asm("rsqrt.approx.f32 %0, %1;" : "=f"(r) : "f"(v + 1e-5f));
  return g * r;
}

template <bool PUBLISH>
__device__ __forceinline__ void transform_weights(int hb, const __nv_bfloat16* __restrict__ w, const __nv_bfloat16* __restrict__ gam,
                                                  const __nv_bfloat16* __restrict__ var, uint8_t* wt, unsigned* sync) {
  constexpr int ROWS = 4 * C * 2, REGION = 21 * ROWS;
  constexpr uint32_t bars = SMEM_BASE + 3 * REGION;
  const int tid = threadIdx.x, lane = tid & 31, warp = __shfl_sync(0xffffffffu, tid >> 5, 0);
  if (warp == 7) {
#pragma unroll 1
    for (int n = 0; n <= 6; n++) {
      asm volatile("bar.sync %0, 256;" ::"r"(n + 1) : "memory");
      if (PUBLISH && lane == 0) {
        asm volatile("fence.proxy.async.global;" ::: "memory");
        asm volatile("red.release.gpu.global.add.u32 [%0], %1;" ::"l"(sync + 32 + n), "n"(GRID / NHELP) : "memory");
      }
      __syncwarp();
    }
    return;
  }
  auto fetch = [&](int batch, int region) {
    const int j = (batch & 1) * 7 + warp, k16 = !(batch & 2) ? j : (j < 12 ? 16 + j : 2 + j);
    const uint32_t bar = bars + 8 * (batch * 7 + warp), dst = SMEM_BASE + region * REGION + warp * 3 * ROWS;
    const __nv_bfloat16* src = w + (size_t)(k16 * 16 + hb * 4) * C;
    asm volatile("{\n.reg .pred p;\nelect.sync _|p, 0xffffffff;\n@p mbarrier.arrive.expect_tx.shared::cta.b64 _, [%2], %4;\n"
                 "@p cp.async.bulk.shared::cluster.global.mbarrier::complete_tx::bytes [%0], [%1], %3, [%2];\n"
                 "@p cp.async.bulk.shared::cluster.global.mbarrier::complete_tx::bytes [%0 + %3], [%1 + %5], %3, [%2];\n"
                 "@p cp.async.bulk.shared::cluster.global.mbarrier::complete_tx::bytes [%0 + 2 * %3], [%1 + 2 * %5], %3, [%2];\n}"
                 ::"r"(dst), "l"(src), "r"(bar), "n"(ROWS), "n"(3 * ROWS), "n"(C * C * 2) : "memory");
  };
  if (lane == 0) {
#pragma unroll
    for (int i = 0; i < 5; i++) mbar_init(bars + 8 * (i * 7 + warp), 1);
    asm volatile("fence.proxy.async.shared::cta;" ::: "memory");
  }
  __syncwarp();
  fetch(0, 0);
  const int d = warp * 64 + (lane & 7) * 8, k = hb * 4 + (lane >> 3);
  const uint4 g4 = *reinterpret_cast<const uint4*>(gam + d), v4 = *reinterpret_cast<const uint4*>(var + d);
  asm volatile("bar.sync 8, 224;" ::: "memory");
  mbar_wait(bars + 8 * warp, 0);
  fetch(1, 1);
  float sc[8];
  const uint32_t gg[4] = {g4.x, g4.y, g4.z, g4.w}, vv[4] = {v4.x, v4.y, v4.z, v4.w};
#pragma unroll
  for (int i = 0; i < 4; i++) { sc[2 * i] = 0.5f * bn_scale(bf_lo(gg[i]), bf_lo(vv[i])); sc[2 * i + 1] = 0.5f * bn_scale(bf_hi(gg[i]), bf_hi(vv[i])); }
  const int blk = d >> 5, half = blk >= 7, pos = !half ? blk : (blk == 7 ? 6 : blk - 8);
  uint8_t* base = wt + half * (NRND * RND) + pos * 1024 + k * 64 + (((lane & 3) ^ ((k >> 1) & 3)) << 4);
#pragma unroll 1
  for (int it = 0; it < 8; it++) {
    const bool pq = it < 4;
    const int j0 = ((it & 1) ^ (it >= 6)) * 7, region = (0x21020210 >> (4 * it)) & 3, batch = (0x41323210 >> (4 * it)) & 7;
    const int step = pq ? WST : 7168, d01 = pq ? 7168 : RND;
    uint8_t* o0 = base + (pq ? 2 + (it & 2) : it < 6 ? 6 : 0) * RND + j0 * step;
    const uint32_t src = SMEM_BASE + region * REGION + (lane >> 3) * (C * 2) + d * 2;
#pragma unroll 1
    for (int j = 0; j < 7; j++) {
      uint32_t a[3][4], r0[4], r1[4];
      mbar_wait(bars + 8 * (batch * 7 + j), 0);
#pragma unroll
      for (int t = 0; t < 3; t++)
        asm volatile("ld.shared.v4.u32 {%0,%1,%2,%3}, [%4];" : "=r"(a[t][0]), "=r"(a[t][1]), "=r"(a[t][2]), "=r"(a[t][3]) : "r"(src + (j * 3 + t) * ROWS) : "memory");
      if (pq) {
#pragma unroll
        for (int i = 0; i < 4; i++) {
          const float l = bf_lo(a[0][i]) + bf_lo(a[2][i]), h = bf_hi(a[0][i]) + bf_hi(a[2][i]), l1 = bf_lo(a[1][i]), h1 = bf_hi(a[1][i]);
          r0[i] = pack_bf16((l + l1) * sc[2 * i], (h + h1) * sc[2 * i + 1]);
          r1[i] = pack_bf16(0.5f * (l - l1) * sc[2 * i], 0.5f * (h - h1) * sc[2 * i + 1]);
        }
      } else {
#pragma unroll
        for (int i = 0; i < 4; i++) {
          r0[i] = pack_bf16(bf_lo(a[0][i]) * sc[2 * i], bf_hi(a[0][i]) * sc[2 * i + 1]);
          r1[i] = pack_bf16(bf_lo(a[2][i]) * sc[2 * i], bf_hi(a[2][i]) * sc[2 * i + 1]);
        }
      }
      *reinterpret_cast<uint4*>(o0 + j * step) = make_uint4(r0[0], r0[1], r0[2], r0[3]);
      *reinterpret_cast<uint4*>(o0 + j * step + d01) = make_uint4(r1[0], r1[1], r1[2], r1[3]);
      if (it == 0 && j == 3) asm volatile("bar.arrive 1, 256;" ::: "memory");
    }
    if (pq || (it & 1)) asm volatile("bar.arrive %0, 256;" ::"r"(pq ? it + 2 : it == 5 ? 6 : 7) : "memory");
    if (it == 0) fetch(2, 2);
    if (it == 1 || it == 4) {
      asm volatile("bar.sync 8, 224;" ::: "memory");
      fetch(it == 1 ? 3 : 4, it == 1 ? 0 : 2);
    }
  }
}

__global__ void transform_kernel(const __nv_bfloat16* __restrict__ w, const __nv_bfloat16* __restrict__ gam, const __nv_bfloat16* __restrict__ var, uint8_t* wt) {
  transform_weights<false>(blockIdx.x, w, gam, var, wt, nullptr);
}

constexpr uint64_t DESC_HI = ((uint64_t)2 << 62) | ((uint64_t)(512 >> 4) << 32) | ((uint64_t)(1024 >> 4) << 16);
constexpr uint64_t DESCA_HI = ((uint64_t)1 << 62) | ((uint64_t)(1024 >> 4) << 32) | ((uint64_t)(4096 >> 4) << 16);
__device__ __forceinline__ constexpr uint64_t raw_desc(int slot, int tap) { return DESCA_HI | (uint64_t)((SMEM_BASE + OFF_W + slot * WRAW + tap * 2048) >> 4); }
__device__ __forceinline__ constexpr uint64_t w_desc(int slot, int sub) { return DESC_HI | (uint64_t)((SMEM_BASE + OFF_W + slot * WST + sub * 7168) >> 4); }

struct Raw { uint32_t q[4], e[2]; };

template <bool INSYNC>
__global__ void __launch_bounds__(256, 1)
conv_bn_silu_kernel(const __nv_bfloat16* __restrict__ w, const __nv_bfloat16* __restrict__ gam, const __nv_bfloat16* __restrict__ var,
                    const __nv_bfloat16* __restrict__ bet, const __nv_bfloat16* __restrict__ mean, unsigned* sync, uint8_t* wt,
                    const __nv_bfloat16* __restrict__ x,
                    const __grid_constant__ CUtensorMap mx, const __grid_constant__ CUtensorMap mwa,
                    const __grid_constant__ CUtensorMap mwb, const __grid_constant__ CUtensorMap mx2, const __grid_constant__ CUtensorMap mo) {
  extern __shared__ __align__(1024) uint8_t smem_raw[];
  constexpr uint32_t sb = SMEM_BASE;
  const int tid = threadIdx.x, lane = tid & 31;
  const int warp = __shfl_sync(0xffffffffu, tid >> 5, 0);
  if (INSYNC && ((blockIdx.x >> 1) == HA || (blockIdx.x >> 1) == HB)) {
    transform_weights<true>((blockIdx.x & 1) + 2 * ((blockIdx.x >> 1) == HB), w, gam, var, wt, sync);
    return;
  }
  auto work_id = [](int b) {
    if (INSYNC) b = b - 2 * ((b >> 1) > HA) - 2 * ((b >> 1) > HB);
    b = (b & 1) | ((b & 14) << 3) | ((b >> 4) << 1);
    return b;
  };
  int bid = work_id(blockIdx.x);
  int half = bid & 1, pair = bid >> 1;

  auto load_x = [&](int slot, int t, int h, bool pred) {
    if (slot < 3) tma_load_x(sb + OFF_X + slot * XSLOT, &mx, sb + BAR_XFULL + 8 * slot, XSLOT, slot * 64, 256, h, pair, t, pred);
    else tma_load_x(sb + OFF_X + 3 * XSLOT, &mx2, sb + BAR_XFULL + 24, XSLOT / 2, 192, 32, h, pair, t, pred);
  };
  auto load_w_raw = [&](int st, bool pred) {
    tma_load_w_raw(sb + OFF_W + (st % 7) * WRAW, &mwa, &mwb, sb + BAR_WFULL + 8 * (st % 7), ((st + 12) % 14) * 16, half * 4, 192 + half * 32, pred);
  };

  if (warp == 7) {
    const uint32_t c0 = clock();
    if (lane == 0) {
      asm volatile("prefetch.tensormap [%0];" ::"l"(&mx2) : "memory");
      asm volatile("prefetch.tensormap [%0];" ::"l"(&mwa) : "memory");
      asm volatile("prefetch.tensormap [%0];" ::"l"(&mwb) : "memory");
      asm volatile("prefetch.tensormap [%0];" ::"l"(&mx) : "memory");
      if (smem_u32(smem_raw) != SMEM_BASE) __trap();
#pragma unroll
      for (int i = 0; i < NBARS; i++) mbar_init(sb + OFF_BAR + 8 * i, i == 15 ? 7 : (i >= 7 && i < 11) ? 32 : 1);
      asm volatile("fence.mbarrier_init.release.cluster;" ::: "memory");
      asm volatile("fence.proxy.async.shared::cta;" ::: "memory");
    }
    __syncwarp();
    load_x(3, 0, 0, true);
    load_w_raw(0, true);
    load_w_raw(1, true);
    while ((uint32_t)clock() - c0 < 900) {}
    __syncwarp();
    load_x(0, 0, 0, true);
#pragma unroll
    for (int i = 2; i < NWS; i++) load_w_raw(i, true);
    if (lane == 0) asm volatile("cp.async.bulk.prefetch.L2.global [%0], %1;" ::"l"(w + bid * (3 * C * C / GRID)), "n"(3 * C * C * 2 / GRID) : "memory");
    __syncwarp();
  } else {
    const int d = half == 0 ? tid : (tid < 192 ? 256 + tid : 32 + tid);
    const __nv_bfloat16 pg = gam[d], pv = var[d], pb = bet[d], pm = mean[d];
    const float sc = bn_scale(__bfloat162float(pg), __bfloat162float(pv));
    const float sh = __bfloat162float(pb) - __bfloat162float(pm) * sc;
    const uint32_t po = (tid >> 4) * 64 + ((tid >> 1) & 3) * 16 + ((tid >> 3) & 1) * 8 + (tid & 1) * 4;
    asm volatile("st.shared.f32 [%0], %1;" ::"r"(sb + OFF_SCALE + po), "f"(0.5f * sc) : "memory");
    asm volatile("st.shared.f32 [%0], %1;" ::"r"(sb + OFF_SHIFT + po), "f"(0.5f * sh) : "memory");
  }
  __syncthreads();
  asm volatile("mov.u32 %0, %%ctaid.x;" : "=r"(bid));
  bid = work_id(bid);
  half = bid & 1; pair = bid >> 1;
  const uint8_t* wsrc = wt + half * (NRND * RND);

  const bool w0 = warp == 0, w7 = warp == 7;
  const uint32_t kz = warp >> 3;
  uint32_t sink = kz, tclk = kz, tclk2 = kz, tclk3 = kz;
#define W7 ((warp | sink) == 7)
  auto lane_unique = [&]() {
    uint32_t l;
    asm volatile("mov.u32 %0, %%laneid;" : "=r"(l));
    return l | sink;
  };
  uint32_t lb[4], lb2 = 0;
#pragma unroll
  for (int i = 0; i < 4; i++) {
    lb[i] = (sb + OFF_X + (warp * 4 + (lane >> 4) * 2) * 1024 + (lane & 7) * 128 + ((((lane >> 3) & 1) ^ (lane & 7)) << 4)) ^ (i << 5);
    asm volatile("" : "+r"(lb[i]));
  }
  asm volatile("{\n.reg .pred p;\nsetp.ne.u32 p, %4, 0;\n@p st.shared.v4.u32 [%4], {%0,%1,%2,%3};\n}" ::"r"(lb[0]), "r"(lb[1]), "r"(lb[2]), "r"(lb[3]), "r"(kz) : "memory");
  auto xaddr = [&](int j) -> uint32_t {
    if (j < 12) return lb[j & 3] + (j >> 2) * XSLOT;
    if (j == 12) {
      const uint32_t l = lb[0] | sink;
      lb2 = ((l >> 1) & ~63u) + (((l >> 4) & 0x30) ^ ((l ^ (l >> 3)) & 0x10));
      asm volatile("" : "+r"(lb2));
    } else {
      lb2 ^= 32;
    }
    return lb2 + ((sb + OFF_X) / 2 + 3 * XSLOT);
  };
  auto xp = [](int j) { return j < 12 ? 1024 : 512; };
  auto x_wait = [&](int slot, int par) { mbar_wait(sb + BAR_XFULL + 8 * slot, par); };

  float acc0[112], acc1[112];
  Raw r0, r1;
  const uint32_t ma = w0 ? 0u : ~0u, mb = w7 ? 0u : ~0u;
  auto load_a = [&](Raw& r, int j, uint32_t a) { ldsm4(a + xp(j), r.q); ldsm2(a - xp(j), r.e); };
  auto load_b = [&](Raw& r, int j, uint32_t a) { ldsm4(a, r.q); ldsm2(a + 4 * xp(j), r.e); };
  asm volatile(".reg .b32 FA0, FA1, FA2, FA3;");
#define SCHED() do { uint32_t t_; asm volatile("mov.u32 %1, %%clock;\nand.b32 %0, %0, %2;" : "+r"(sink), "=r"(t_) : "r"(tclk3) : "memory"); \
    tclk3 = tclk2; tclk2 = tclk; tclk = t_; } while (0)
#define WAIT() do { wg_wait0(); SCHED(); } while (0)
#define FRAG(op, a0, b0, a1, b1, a2, b2, a3, b3) do { \
    asm volatile(op " FA0, %0, %1;\n" op " FA1, %2, %3;\n" op " FA2, %4, %5;\n" op " FA3, %6, %7;" \
                 ::"r"(a0), "r"(b0), "r"(a1), "r"(b1), "r"(a2), "r"(b2), "r"(a3), "r"(b3)); wg_fence(); } while (0)
#define FRAG_A(r) FRAG("sub.rn.bf16x2", r.e[0] & ma, r.q[0], r.q[0], r.q[2], r.e[1] & ma, r.q[1], r.q[1], r.q[3])
#define FRAG_B(r) FRAG("sub.rn.bf16x2", r.q[2], r.q[0], r.e[0] & mb, r.q[2], r.q[3], r.q[1], r.e[1] & mb, r.q[3])
#define FRAG_P FRAG("add.rn.bf16x2", r1.q[0], r0.q[0], r1.q[2], r0.q[2], r1.q[1], r0.q[1], r1.q[3], r0.q[3])
#define FRAG_Q FRAG("sub.rn.bf16x2", r0.q[0], r1.q[0], r0.q[2], r1.q[2], r0.q[1], r1.q[1], r0.q[3], r1.q[3])
#define MMA(acc, desc, FR) do { FR; wgmma_acc(acc, desc); wg_commit(); } while (0)
#define FBAR(u) (sb + BAR_WFULL + 8 * (((u) + 1) % 7))
#define FPAR(u, par) ((par) ^ ((u) == 6))

  uint32_t toke = 0;
  auto w_duty1 = [&](int u, int par) {
    if (u & 1) return;
    asm volatile("{\n.reg .pred p;\nsetp.ne.u32 p, %3, 0;\n@p mbarrier.arrive.shared::cta.b64 _, [%1];\n"
                 "mbarrier.test_wait.parity.shared::cta.b64 p, [%1], %2;\nselp.u32 %0, 1, 0, p;\n}"
                 : "=r"(toke) : "r"(sb + BAR_WEMPTY + 4 * ((u + 6) & 7)), "r"(par ^ (u == 0)), "r"((uint32_t)w0) : "memory");
  };
  auto w_duty2 = [&](int u, int par, const uint8_t* src, int rnd, bool pred, bool load = true, bool keep = false) {
    if (u & 1) return;
    const int slot = (u + 6) % 7, nload = !load ? 0 : u > 0 ? 2 : 1;
    asm volatile(
        "{\n.reg .pred p, q, r;\n.reg .u32 c, n;\n.reg .u64 a;\n"
        "setp.eq.u32 p, %5, 0;\n@p bra.uni LAB_SKIP;\nsetp.ne.u32 p, %9, 0;\n@p bra.uni LAB_GO;\n" SPIN("%0", "%1", "LAB_GO")
        "LAB_GO:\n"
        "setp.eq.u32 q, %8, 0;\n@q bra.uni LAB_SKIP;\n"
        "elect.sync _|p, 0xffffffff;\n"
        "setp.ne.u32 r, %10, 0;\nselp.u32 n, 0, %6, r;\n"
        "setp.eq.u32 q, %8, 1;\n@q bra.uni LAB_A1;\n"
        "@p mbarrier.arrive.expect_tx.shared::cta.b64 _, [%4 + -8], n;\n"
        "LAB_A1:\n"
        "@p mbarrier.arrive.expect_tx.shared::cta.b64 _, [%4], n;\n"
        "@r bra.uni LAB_SKIP;\n"
        "add.u64 a, %3, %7;\n"
        "@q bra.uni LAB_ONE;\n"
        "@p cp.async.bulk.shared::cluster.global.mbarrier::complete_tx::bytes [%2 + -14336], [a + -14336], %6, [%4 + -8];\n"
        "LAB_ONE:\n"
        "@p cp.async.bulk.shared::cluster.global.mbarrier::complete_tx::bytes [%2], [a], %6, [%4];\n"
        "LAB_SKIP:\n}"
        ::"r"(sb + BAR_WEMPTY + 4 * ((u + 6) & 7)), "r"(par ^ (u == 0)), "r"(sb + OFF_W + slot * WST), "l"(src),
          "r"(sb + BAR_WFULL + 8 * slot), "r"((uint32_t)pred), "n"(WST), "l"((uint64_t)(rnd * RND + slot * WST)), "r"(nload),
          "r"(toke), "r"((uint32_t)keep) : "memory");
  };

  uint32_t sta = 0;
#define LOAD_PAR(dst, addr) asm volatile("ld.shared.v4.b32 {%0,%1,%2,%3}, [%4];" : "=r"(dst[0]), "=r"(dst[1]), "=r"(dst[2]), "=r"(dst[3]) : "r"(addr))
  auto par_base = [&](uint32_t off) {
    uint32_t p = sb + off + (lane_unique() & 3) * 16;
    asm volatile("" : "+r"(p));
    return p;
  };
  auto drain_act = [&](float (&a)[112], int j) {
#pragma unroll
    for (int i = 0; i < 8; i++)
      asm volatile("{\n.reg .f32 t;\ntanh.approx.f32 t, %0;\nfma.rn.f32 %0, %0, t, %0;\n}" : "+f"(a[8 * j + i]));
  };
  auto drain_out = [&](float (&a)[112], int j, uint32_t buf, uint32_t base) {
    uint32_t o[4];
#pragma unroll
    for (int i = 0; i < 4; i++) o[i] = pack_bf16(a[8 * j + 2 * i], a[8 * j + 2 * i + 1]);
    if (j == 0) {
      const uint32_t l = lane_unique();
      sta = (base | sink) + (l & 15) * 64 + (((l >> 4) ^ ((l >> 1) & 3)) << 4);
      asm volatile("" : "+r"(sta));
    }
    stsm4(((j & 1) ? sta ^ 32 : sta) + buf, o[0], o[1], o[2], o[3]);
  };
#define PROXY_FENCE() asm volatile("fence.proxy.async.shared::cta;" ::: "memory")
  auto store_piece = [&](uint32_t buf, int p, int hf, int t, int odd) {
    tma_store_4d(&mo, buf, p < 6 ? hf * 256 + p * 32 : 192 + hf * 32, (pair + t * (GRID / 2)) * 8, warp * 2, odd);
  };

  unsigned flag = 0, fbase = 0;
  if (INSYNC) asm volatile("{\n.reg .pred p;\nsetp.eq.u32 p, %2, 224;\n@p atom.relaxed.gpu.global.add.u32 %0, [%1], 1;\n}" : "+r"(fbase) : "l"(sync), "r"(tid) : "memory");
  auto flag_sample = [&](int level, bool pred) { if (INSYNC) flag = flag_load(sync, level, W7 && pred); };
  auto flag_check = [&](int level, bool pred) { if (INSYNC) flag_wait(sync, level, flag, fbase, W7 && pred); };

  x_wait(3, 0);
  { const uint32_t a = xaddr(12); load_a(r0, 12, a); load_b(r1, 12, a); }
  mbar_wait(sb + BAR_WFULL, 0);
  {
#pragma unroll
    for (int j = 0; j < 14; j++) {
      const int u = j % 7, rp = j / 7;
      FRAG_A(r0);
      if (j == 0) wgmma_first(acc0, raw_desc(u, 0)); else wgmma_acc(acc0, raw_desc(u, 0));
      wg_commit();
      const int nj = j < 13 ? (j + 13) % 14 : 0;
      if (j < 13 && (nj & 3) == 0) x_wait(nj >> 2, 0);
      const uint32_t na = xaddr(nj);
      if (j < 13) load_a(r0, nj, na); else ldsm4(na + 1024, r0.q);
      const uint32_t tokf = mbar_test(FBAR(u), FPAR(u, rp));
      if (j > 0) w_duty1(u, rp);
      if (j == 5) fbase = (__shfl_sync(0xffffffffu, fbase, 0) & ~(GRID - 1)) + GRID;
      if (j == 7 || j == 11) flag_sample(j == 11, true);
      if (j == 9 || j == 13) flag_check(j == 13, true);
      wg_wait0();
      FRAG_B(r1);
      if (j == 0) wgmma_first(acc1, raw_desc(u, 1)); else wgmma_acc(acc1, raw_desc(u, 1));
      wg_commit();
      if (j < 13) load_b(r1, nj, na); else ldsm4(na, r1.q);
      if (j > 0) w_duty2(u, rp, wsrc, 2, w7, j > 8);
      if (j > 0 && j < 8 && !(u & 1)) { if (u > 0) load_w_raw(j + 5, w7); load_w_raw(j + 6, w7); }
      if (j == 0) load_x(1, 0, 0, w7);
      if (j == 3) load_x(2, 0, 0, w7);
      if (j == 5) asm volatile("{\n.reg .pred p;\nsetp.ne.u32 p, %1, 0;\n@p prefetch.tensormap [%0];\n}" ::"l"(&mo), "r"((uint32_t)w7) : "memory");
      if (j == 8) prefetch_tensor_3d(&mx, 256 + half * 64, pair * 8, w7);
      if (j == 12) prefetch_tensor_3d(&mx, 384, pair * 8, w7);
      mbar_wait_tok(FBAR(u), FPAR(u, rp), tokf);
      wg_wait0();
    }
  }
  sink &= tclk2 & tclk3;
  fence_acc(acc0); fence_acc(acc1);
  {
    const uint32_t ps = par_base(OFF_SCALE);
#pragma unroll
    for (int j = 0; j < 14; j++) {
      uint32_t s4[4];
      LOAD_PAR(s4, ps + j * 64);
#pragma unroll
      for (int i = 0; i < 8; i++) {
        const float sc = __uint_as_float(s4[(i >> 2) * 2 + (i & 1)]);
        asm volatile("{\n.reg .f32 n;\nmul.rn.f32 %1, %1, %2;\nfma.rn.f32 %0, %0, %2, %1;\nneg.f32 n, %1;\nfma.rn.f32 %1, %0, 0f3F000000, n;\n}"
                     : "+f"(acc0[8 * j + i]), "+f"(acc1[8 * j + i]) : "f"(sc));
      }
    }
  }

  int s = sink;
#define STEP_BEGIN() \
    s = __shfl_sync(0xffffffffu, s, 0);     \
    const int tile = s >= 5; (void)tile; \
    sink = tclk = tclk2 = tclk3 = kz & s; \
    const uint32_t rr = (uint32_t)(0x01024677642ull >> (4 * s)); \
    const uint8_t* wcur = wsrc + (rr & 15) * RND;             \
    const uint8_t* wnext = wsrc + ((rr >> 4) & 15) * RND
#define STEP_END() do { s += 1 + (sink & tclk2 & tclk3); } while (0)
step_pq:
  {
    STEP_BEGIN();
    const int k = s & 1;
    const uint32_t ps = par_base(OFF_SHIFT);
#pragma unroll
    for (int j = 0; j < 14; j++) {
      const int u = j % 7, rp = j / 7;
      MMA(acc0, w_desc(u, 0), FRAG_P);
      if (j < 13 && ((j + 1) & 3) == 0) x_wait((j + 1) >> 2, k);
      if (j == 13) x_wait(0, 1);
      uint32_t s4[4];
      LOAD_PAR(s4, ps + j * 64);
      const uint32_t tokf = mbar_test(FBAR(u), FPAR(u, rp));
      w_duty1(u, rp);
      if (u == 0) flag_sample(2 + 2 * k + rp, tile == 0);
      if (u == 2) flag_check(2 + 2 * k + rp, tile == 0);
      wg_wait0();
      MMA(acc1, w_desc(u, 1), FRAG_Q);
      { const uint32_t a = xaddr((j + 1) % 14); ldsm4(a, r1.q); ldsm4(a + xp((j + 1) % 14), r0.q); }
      if (j == 13) ldsm2(xaddr(0) - 1024, r0.e);
#pragma unroll
      for (int i = 0; i < 8; i++)
        asm volatile("add.rn.f32 %0, %0, %1;" : "+f"(acc0[8 * j + i]) : "f"(__uint_as_float(s4[(i >> 2) * 2 + (i & 1)])));
      w_duty2(u, rp, j < 8 ? wcur : wnext, j > 0 && j < 8, w7);
      if (j == 0) load_x(3, tile, tile ^ 1, k == 1 && W7);
      if (j == 4 || j == 9 || j == 13) load_x(j >> 2 == 1 ? 0 : j >> 2 == 2 ? 1 : 2, tile, tile ^ 1, k == 0 && W7);
      if (j == 3 || j == 6 || j == 10 || j == 13)
        prefetch_l2(x, bid, k, GRID * 8 + (j >> 2), W7 && tile == 0);
      if (j == 1 || j == 5 || j == 8 || j == 12)
        tma_load_x(sb + OFF_STG, &mx2, sb + BAR_WARM, XSLOT / 2, 192 + (j >> 2) * 32, 128, k, pair, 1, W7 && (j == 1 ? s == 1 : tile == 0));
      mbar_wait_tok(FBAR(u), FPAR(u, rp), tokf);
      wg_wait0();
    }
    STEP_END();
    if (s & 1) goto step_pq;
  }
step_bf:
  {
    s = __shfl_sync(0xffffffffu, s, 0);
    fence_acc(acc0); fence_acc(acc1);
#pragma unroll
    for (int i = 0; i < 112; i++)
      asm volatile("{\n.reg .f32 n;\nneg.f32 n, %0;\nfma.rn.f32 %0, %1, 0f3F000000, n;\n}" : "+f"(acc1[i]) : "f"(acc0[i]));
    if (s == 6) goto step_pq;
  }
step_a:
  {
    STEP_BEGIN();
    const int ap = s == 5;
    const float cs = ap ? 1.f : -1.f;
    auto mix = [&](int j) {
#pragma unroll
      for (int i = 0; i < 8; i++) asm volatile("fma.rn.f32 %0, %1, %2, %0;" : "+f"(acc0[8 * j + i]) : "f"(acc1[8 * j + i]), "f"(cs));
    };
#pragma unroll
    for (int u = 0; u < 7; u++) {
      FRAG_A(r0);
      if (u == 0) wgmma_sd(acc0, w_desc(u, 0), ap ^ 1); else wgmma_acc(acc0, w_desc(u, 0));
      wg_commit();
      if (u == 0) load_a(r1, 1, xaddr(1));
      if (u < 6) load_a(r0, 2 * u + 2, xaddr(2 * u + 2)); else ldsm4(xaddr(0) + 1024, r0.q);
      const uint32_t tokf = mbar_test(FBAR(u), FPAR(u, ap));
      w_duty1(u, ap);
      if (u == 3) flag_sample(6, ap);
      wg_wait0();
      mix(2 * u);
      MMA(acc0, w_desc(u, 1), FRAG_A(r1));
      if (u < 6) load_a(r1, 2 * u + 3, xaddr(2 * u + 3)); else load_b(r1, 0, xaddr(0));
      if (u == 5) flag_check(6, ap);
      w_duty2(u, ap, u ? wnext : wcur, 0, w7);
      mbar_wait_tok(FBAR(u), FPAR(u, ap), tokf);
      wg_wait0();
      mix(2 * u + 1);
    }
    STEP_END();
    if (s == 6) goto step_bf;
  }
step_d:
  {
    STEP_BEGIN();
    const int d = s == 4, par = d ^ 1;
    const uint32_t stg = sb + OFF_STG + (warp | sink) * 2048;
    const int hf = half | sink;
    fence_acc(acc0);
#pragma unroll
    for (int u = 0; u < 7; u++) {
      const int fpar = u < 6 ? par : d ^ tile;
      const uint32_t xbar = sb + BAR_XFULL + 8 * (u < 6 ? (u + 1) >> 1 : 0);
      const int xpar = u < 6 ? par : tile;
      FRAG_B(r1);
      if (u == 0) wgmma_sd(acc1, w_desc(u, 0), par); else wgmma_acc(acc1, w_desc(u, 0));
      wg_commit();
      load_b(r1, 2 * u + 1, xaddr(2 * u + 1));
      const uint32_t tokf = mbar_test(FBAR(u), fpar);
      uint32_t tokx = 0;
      if ((u & 1) || u == 6) tokx = mbar_test(xbar, xpar);
      w_duty1(u, par);
      if (u > 0) drain_out(acc0, 2 * u - 1, ((u - 1) & 1) * 1024, stg);
      drain_act(acc0, 2 * u);
      if (u > 0) PROXY_FENCE();
      if (!(u & 1)) { w_duty2(u, par, wcur, 0, W7 && s == 3 + (u == 0), false); load_x(((u >> 1) + 3) & 3, 1, 1, W7 && s == 3 + (u == 0)); }
      if ((u & 1) || u == 6) mbar_wait_tok(xbar, xpar, tokx);
      WAIT();
      FRAG_B(r1); wgmma_acc(acc1, w_desc(u, 1)); wg_commit();
      load_b(r1, (2 * u + 2) % 14, xaddr((2 * u + 2) % 14));
      if (u > 0) store_piece(stg + ((u - 1) & 1) * 1024, u - 1, hf, tile, d);
      if (u == 0) { mbar_wait(sb + BAR_WARM, 0); asm volatile("cp.async.bulk.wait_group.read 0;" ::: "memory"); }
      if (u > 1) asm volatile("cp.async.bulk.wait_group.read 1;" ::: "memory");
      __syncwarp();
      drain_out(acc0, 2 * u, (u & 1) * 1024, stg);
      drain_act(acc0, 2 * u + 1);
      if (u == 6) { drain_out(acc0, 13, 0, stg); PROXY_FENCE(); store_piece(stg, 6, hf, tile, d); load_a(r0, 0, xaddr(0)); }
      w_duty2(u, par, u ? wnext : wcur, 0, W7 && (u == 0 || tile == 0), true, s == 3 + (u == 0));
      mbar_wait_tok(FBAR(u), fpar, tokf);
      WAIT();
    }
    fence_acc(acc1);
    STEP_END();
    if (s == 4) {
#pragma unroll
      for (int i = 0; i < 112; i++) asm volatile("mov.b32 %0, %1;" : "=f"(acc0[i]) : "f"(acc1[i]));
      goto step_d;
    }
    if (s == 5) {
#pragma unroll
      for (int i = 0; i < 24; i++) acc0[i] = 0.f;
      fence_acc(acc0);
      goto step_a;
    }
  }
  {
    const uint32_t fb = sb + OFF_X + (warp >> 2) * 18432 + (warp & 3) * 3072;
#pragma unroll
    for (int u = 0; u < 7; u++) {
      const uint32_t buf = (u / 3) * XSLOT + (u % 3) * 1024;
      if (u == 0) { drain_act(acc1, 0); drain_act(acc1, 1); }
      drain_out(acc1, 2 * u, buf, fb);
      drain_out(acc1, 2 * u + 1, buf, fb);
      if (u < 6) { drain_act(acc1, 2 * u + 2); drain_act(acc1, 2 * u + 3); }
      PROXY_FENCE();
      store_piece(fb + buf, u, half | sink, 1, 1);
    }
  }
  asm volatile("cp.async.bulk.wait_group.read 0;" ::: "memory");
}

typedef CUresult (*EncodeFn)(CUtensorMap*, CUtensorMapDataType, cuuint32_t, void*, const cuuint64_t*, const cuuint64_t*, const cuuint32_t*,
                             const cuuint32_t*, CUtensorMapInterleave, CUtensorMapSwizzle, CUtensorMapL2promotion, CUtensorMapFloatOOBfill);

}

extern "C" void kernel_launch(void* const* d_in, const int* in_sizes, int n_in, void* d_out, int out_size) {
  (void)in_sizes; (void)n_in; (void)out_size;
  const __nv_bfloat16* x = (const __nv_bfloat16*)d_in[0];
  const __nv_bfloat16* w = (const __nv_bfloat16*)d_in[1];
  static EncodeFn enc = nullptr;
  static int insync = 0;
  static unsigned* p_sync = nullptr;
  static uint8_t* p_wt = nullptr;
  if (!enc) {
    cudaDriverEntryPointQueryResult qr;
    cudaGetDriverEntryPoint("cuTensorMapEncodeTiled", (void**)&enc, cudaEnableDefault, &qr);
    cudaFuncSetAttribute(conv_bn_silu_kernel<true>, cudaFuncAttributeMaxDynamicSharedMemorySize, SMEM_BYTES);
    cudaFuncSetAttribute(conv_bn_silu_kernel<false>, cudaFuncAttributeMaxDynamicSharedMemorySize, SMEM_BYTES);
    cudaGetSymbolAddress((void**)&p_sync, g_sync);
    cudaFuncSetAttribute(transform_kernel, cudaFuncAttributeMaxDynamicSharedMemorySize, SMEM_BYTES);
    cudaGetSymbolAddress((void**)&p_wt, g_wt);
    int dev = 0, sms = 0, occ = 0;
    cudaGetDevice(&dev);
    cudaDeviceGetAttribute(&sms, cudaDevAttrMultiProcessorCount, dev);
    if (cudaOccupancyMaxActiveBlocksPerMultiprocessor(&occ, conv_bn_silu_kernel<true>, 256, SMEM_BYTES) != cudaSuccess) occ = 0;
    (void)cudaGetLastError();
    insync = sms * occ >= GRID + NHELP;
  }
  CUtensorMap mx, mx2, mwa, mwb, mo;
  const cuuint32_t es[4] = {1, 1, 1, 1};
  {
    cuuint64_t gd[3] = {C, NB, S}; cuuint64_t gs[2] = {(cuuint64_t)S * C * 2, (cuuint64_t)C * 2};
    cuuint32_t bx[3] = {64, 8, 32}, bx2[3] = {32, 8, 32};
    enc(&mx, CU_TENSOR_MAP_DATA_TYPE_BFLOAT16, 3, (void*)x, gd, gs, bx, es, CU_TENSOR_MAP_INTERLEAVE_NONE, CU_TENSOR_MAP_SWIZZLE_128B,
        CU_TENSOR_MAP_L2_PROMOTION_L2_128B, CU_TENSOR_MAP_FLOAT_OOB_FILL_NONE);
    enc(&mx2, CU_TENSOR_MAP_DATA_TYPE_BFLOAT16, 3, (void*)x, gd, gs, bx2, es, CU_TENSOR_MAP_INTERLEAVE_NONE, CU_TENSOR_MAP_SWIZZLE_64B,
        CU_TENSOR_MAP_L2_PROMOTION_NONE, CU_TENSOR_MAP_FLOAT_OOB_FILL_NONE);
  }
  {
    cuuint64_t gd[4] = {C, NB, S / 2, 2}; cuuint64_t gs[3] = {(cuuint64_t)S * C * 2, (cuuint64_t)C * 4, (cuuint64_t)C * 2};
    cuuint32_t bo[4] = {32, 8, 2, 1};
    enc(&mo, CU_TENSOR_MAP_DATA_TYPE_BFLOAT16, 4, d_out, gd, gs, bo, es, CU_TENSOR_MAP_INTERLEAVE_NONE, CU_TENSOR_MAP_SWIZZLE_64B,
        CU_TENSOR_MAP_L2_PROMOTION_NONE, CU_TENSOR_MAP_FLOAT_OOB_FILL_NONE);
  }
  {
    cuuint64_t gd[4] = {64, C, 2, 7}; cuuint64_t gs[3] = {(cuuint64_t)C * 2, (cuuint64_t)2 * C * C * 2, 128};
    cuuint32_t bx[4] = {64, 16, 2, 3};
    enc(&mwa, CU_TENSOR_MAP_DATA_TYPE_BFLOAT16, 4, (void*)w, gd, gs, bx, es, CU_TENSOR_MAP_INTERLEAVE_NONE, CU_TENSOR_MAP_SWIZZLE_128B,
        CU_TENSOR_MAP_L2_PROMOTION_L2_128B, CU_TENSOR_MAP_FLOAT_OOB_FILL_NONE);
    cuuint64_t gd2[3] = {256, C, 2}; cuuint64_t gs2[2] = {(cuuint64_t)C * 2, (cuuint64_t)2 * C * C * 2};
    cuuint32_t bx2[3] = {64, 16, 2};
    enc(&mwb, CU_TENSOR_MAP_DATA_TYPE_BFLOAT16, 3, (void*)w, gd2, gs2, bx2, es, CU_TENSOR_MAP_INTERLEAVE_NONE, CU_TENSOR_MAP_SWIZZLE_128B,
        CU_TENSOR_MAP_L2_PROMOTION_L2_128B, CU_TENSOR_MAP_FLOAT_OOB_FILL_NONE);
  }
  const __nv_bfloat16 *mean = (const __nv_bfloat16*)d_in[2], *var = (const __nv_bfloat16*)d_in[3];
  const __nv_bfloat16 *gam = (const __nv_bfloat16*)d_in[4], *bet = (const __nv_bfloat16*)d_in[5];
  if (insync) {
    conv_bn_silu_kernel<true><<<GRID + NHELP, 256, SMEM_BYTES>>>(w, gam, var, bet, mean, p_sync, p_wt, x, mx, mwa, mwb, mx2, mo);
  } else {
    transform_kernel<<<NHELP, 256, SMEM_BYTES>>>(w, gam, var, p_wt);
    conv_bn_silu_kernel<false><<<GRID, 256, SMEM_BYTES>>>(w, gam, var, bet, mean, p_sync, p_wt, x, mx, mwa, mwb, mx2, mo);
  }
}
```
